```python
import torch

def _softmax(x, axis=-1):
    return torch.softmax(x, dim=axis)
def _gelu(x):
    return torch.nn.functional.gelu(x, approximate="tanh")
def _silu(x):
    return torch.nn.functional.silu(x)
def _sigmoid(x):
    return torch.sigmoid(x)
def _layernorm(x, axis=-1, eps=1e-5):
    m = x.mean(dim=axis, keepdim=True)
    v = x.var(dim=axis, keepdim=True, unbiased=False)
    return (x - m) / torch.sqrt(v + eps)
def _scatter_add(tgt, idx, src, axis=0):
    return tgt.clone().index_add_(axis, idx, src)
def _segment_sum(src, seg, n):
    out = torch.zeros((n,) + src.shape[1:], dtype=src.dtype)
    return out.index_add_(0, seg, src)
def _pad(x, pw):
    flat = tuple(v for pair in reversed(pw) for v in pair)
    return torch.nn.functional.pad(x, flat)

kernel_name = 'concat_heads__compressed_kv_cla__ssm_conv_s4d__prompt'

def setup_inputs():

    _w = (lambda a: (lambda t: t.to(torch.bfloat16) if t.is_floating_point() else t)(torch.as_tensor(a)))
    def _A_setup():
        B, H, Sq, Sk, D, M = 1, 32, 2048, 2048, 128, 512
        Dc = 4 * D
        return {
            "x": _w((lambda *s: torch.randn(*s, dtype=torch.bfloat16) * 3.2)(B, Sq, M)),
            "c_kv": _w((lambda *s: torch.randn(*s, dtype=torch.bfloat16) * 0.1)(B, Sk, Dc)),
            "w_q": _w((lambda *s: torch.randn(*s, dtype=torch.bfloat16) * 6.4)(M, H, D) * (M ** -0.5)),
            "w_uk": _w((lambda *s: torch.randn(*s, dtype=torch.bfloat16) * 6.4)(Dc, H, D) * (Dc ** -0.5)),
            "w_uv": _w((lambda *s: torch.randn(*s, dtype=torch.bfloat16) * 0.1)(Dc, H, D) * (Dc ** -0.5)),
            "w_o": _w((lambda *s: torch.randn(*s, dtype=torch.bfloat16) * 0.1)(H, D, M) * ((H * D) ** -0.5)),
        }
    _A_in = _A_setup()

    def _B_setup():
        Bsz, L, D, N = 1, 2048, 512, 128
        return {
            "u": _w((lambda *s: torch.randn(*s, dtype=torch.bfloat16) * 0.05)(Bsz, L, D)),
            "log_A_real": _w((lambda *s: torch.randn(*s, dtype=torch.bfloat16) * 6.4)(D, N) * 0.5),
            "A_imag": _w((lambda *s: torch.randn(*s, dtype=torch.bfloat16) * 0.05)(D, N) * 3.14),
            "C_real": _w((lambda *s: torch.randn(*s, dtype=torch.bfloat16) * 0.05)(D, N) / N ** 0.5),
            "C_imag": _w((lambda *s: torch.randn(*s, dtype=torch.bfloat16) * 0.05)(D, N) / N ** 0.5),
            "log_dt": _w((lambda *s: torch.randn(*s, dtype=torch.bfloat16) * 0.05)(D) * 0.5 - 4.0),
            "D_skip": _w((lambda *s: torch.randn(*s, dtype=torch.bfloat16) * 0.05)(D)),
        }
    _B_in = _B_setup()

    return {
        "A_x": _A_in["x"],
        "A_c_kv": _A_in["c_kv"],
        "A_w_q": _A_in["w_q"],
        "A_w_uk": _A_in["w_uk"],
        "A_w_uv": _A_in["w_uv"],
        "A_w_o": _A_in["w_o"],
        "B_u": _B_in["u"],
        "B_log_A_real": _B_in["log_A_real"],
        "B_A_imag": _B_in["A_imag"],
        "B_C_real": _B_in["C_real"],
        "B_C_imag": _B_in["C_imag"],
        "B_log_dt": _B_in["log_dt"],
        "B_D_skip": _B_in["D_skip"],
    }

def reference(A_x, A_c_kv, A_w_q, A_w_uk, A_w_uv, A_w_o, B_u, B_log_A_real, B_A_imag, B_C_real, B_C_imag, B_log_dt, B_D_skip):
    def _A_ref(x, c_kv, w_q, w_uk, w_uv, w_o):
        B, Sq, M = x.shape[0], x.shape[1], x.shape[2]
        Sk = c_kv.shape[1]
        H, D = w_q.shape[1], w_q.shape[2]
        q = torch.einsum("bqm,mhd->bhqd", x, w_q)
        k = torch.einsum("bkc,chd->bhkd", c_kv, w_uk)
        v = torch.einsum("bkc,chd->bhkd", c_kv, w_uv)
        scores = torch.einsum("bhqd,bhkd->bhqk", q, k) * (D ** -0.5)
        off = Sk - Sq
        qi = torch.arange(Sq)[:, None]
        kj = torch.arange(Sk)[None, :]
        cmask = kj <= (qi + off)
        scores = torch.where(cmask[None, None], scores, -1e9)
        p = _softmax(scores, axis=-1)
        ctx = torch.einsum("bhqk,bhkd->bhqd", p, v)
        return torch.einsum("bhqd,hdm->bqm", ctx, w_o)

    def _B_ref(u, log_A_real, A_imag, C_real, C_imag, log_dt, D_skip):
        L = u.shape[1]
        dt = torch.exp(log_dt)
        A = -torch.exp(log_A_real) + 1j * A_imag
        C = (C_real + 1j * C_imag) * dt[:, None]
        pos = (lambda x, dt: x.to(dt))(torch.arange(L), log_dt.dtype)
        P = torch.exp((A * dt[:, None])[:, :, None] * pos[None, None, :])
        K = 2.0 * torch.einsum("dn,dnl->dl", C, P).real
        L2 = 2 * L
        u_t = (lambda x, *d: x.permute(*d))(u, 0, 2, 1)
        Kf = (lambda x, *a, **k: torch.fft.rfft(x.float(), *a, **k))(K, L2)
        Uf = (lambda x, *a, **k: torch.fft.rfft(x.float(), *a, **k))(u_t, L2)
        y = (lambda x, *a, **k: torch.fft.irfft(x, *a, **k).to(torch.bfloat16))(Uf * Kf[None, :, :], L2)[:, :, :L]
        y = (lambda x, *d: x.permute(*d))(y, 0, 2, 1)
        return y + u * D_skip[None, None, :]

    a = _A_ref(A_x, A_c_kv, A_w_q, A_w_uk, A_w_uv, A_w_o)
    b = _B_ref(B_u, B_log_A_real, B_A_imag, B_C_real, B_C_imag, B_log_dt, B_D_skip)
    return torch.concatenate([a, b], axis=-1)
```

```cpp
#include <cuda_runtime.h>
#include <cuda_bf16.h>
#include <cuda.h>
#include <stdint.h>

typedef __nv_bfloat16 bf16;

constexpr int SEQ = 2048, DM = 512, NH = 32, HD = 128, DC = 512;
constexpr int SSM_D = 512, SSM_N = 128;

__device__ __align__(1024) bf16 g_kv[(size_t)2 * NH * SEQ * HD];
__device__ __align__(1024) bf16 g_ctx[(size_t)SEQ * NH * HD];

#define TRACE_BEGIN(k)
#define TRACE_END(k, cond)
__device__ __forceinline__ uint32_t smem_u32(const void* p) { return (uint32_t)__cvta_generic_to_shared(p); }

__device__ __forceinline__ void mbar_init(uint32_t bar, uint32_t count) {
    asm volatile("mbarrier.init.shared::cta.b64 [%0], %1;" ::"r"(bar), "r"(count) : "memory");
}
__device__ __forceinline__ void mbar_expect_tx(uint32_t bar, uint32_t bytes) {
    asm volatile("mbarrier.arrive.expect_tx.shared::cta.b64 _, [%0], %1;" ::"r"(bar), "r"(bytes) : "memory");
}
__device__ __forceinline__ void mbar_arrive(uint32_t bar) {
    asm volatile("mbarrier.arrive.shared::cta.b64 _, [%0];" ::"r"(bar) : "memory");
}
__device__ __forceinline__ void mbar_arrive_cluster(uint32_t bar, uint32_t cta) {
    asm volatile("{\n.reg .b32 ra;\nmapa.shared::cluster.u32 ra, %0, %1;\n"
                 "mbarrier.arrive.shared::cluster.b64 _, [ra];\n}\n" ::"r"(bar), "r"(cta) : "memory");
}
__device__ __forceinline__ bool mbar_try_wait(uint32_t bar, uint32_t parity) {
    uint32_t ok;
    asm volatile("{\n.reg .pred p;\nmbarrier.try_wait.parity.shared::cta.b64 p, [%1], %2;\nselp.u32 %0, 1, 0, p;\n}\n"
                 : "=r"(ok) : "r"(bar), "r"(parity) : "memory");
    return ok != 0;
}
__device__ __forceinline__ void mbar_wait(uint32_t bar, uint32_t parity) {
    if (mbar_try_wait(bar, parity)) return;
    uint32_t spins = 0;
    while (!mbar_try_wait(bar, parity)) {
        if (++spins > (1u << 22)) { asm volatile("st.global.u32 [%0], %1;" ::"l"(0ull), "r"(0) : "memory"); break; }
    }
}
__device__ __forceinline__ bool mbar_try_wait_cluster(uint32_t bar, uint32_t parity) {
    uint32_t ok;
    asm volatile("{\n.reg .pred p;\nmbarrier.try_wait.parity.acquire.cluster.shared::cta.b64 p, [%1], %2;\nselp.u32 %0, 1, 0, p;\n}\n"
                 : "=r"(ok) : "r"(bar), "r"(parity) : "memory");
    return ok != 0;
}
__device__ __forceinline__ void mbar_wait_cluster(uint32_t bar, uint32_t parity) {
    if (mbar_try_wait_cluster(bar, parity)) return;
    uint32_t spins = 0;
    while (!mbar_try_wait_cluster(bar, parity)) {
        if (++spins > (1u << 22)) { asm volatile("st.global.u32 [%0], %1;" ::"l"(0ull), "r"(0) : "memory"); break; }
    }
}
__device__ __forceinline__ void fence_barrier_init() { asm volatile("fence.mbarrier_init.release.cluster;" ::: "memory"); }
__device__ __forceinline__ void fence_proxy_async() { asm volatile("fence.proxy.async.shared::cta;" ::: "memory"); }
__device__ __forceinline__ void cluster_arrive() { asm volatile("barrier.cluster.arrive.release.aligned;" ::: "memory"); }
__device__ __forceinline__ void cluster_wait() { asm volatile("barrier.cluster.wait.acquire.aligned;" ::: "memory"); }
__device__ __forceinline__ uint32_t cluster_ctarank() { uint32_t r; asm volatile("mov.u32 %0, %%cluster_ctarank;" : "=r"(r)); return r; }

__device__ __forceinline__ void tma_load_2d(uint32_t dst, const CUtensorMap* map, uint32_t bar, int c0, int c1) {
    asm volatile("cp.async.bulk.tensor.2d.shared::cluster.global.mbarrier::complete_tx::bytes [%0], [%1, {%3, %4}], [%2];"
                 ::"r"(dst), "l"((uint64_t)map), "r"(bar), "r"(c0), "r"(c1) : "memory");
}
__device__ __forceinline__ void tma_load_2d_mc(uint32_t dst, const CUtensorMap* map, uint32_t bar, int c0, int c1, uint16_t mask) {
    asm volatile("cp.async.bulk.tensor.2d.shared::cluster.global.mbarrier::complete_tx::bytes.multicast::cluster [%0], [%1, {%3, %4}], [%2], %5;"
                 ::"r"(dst), "l"((uint64_t)map), "r"(bar), "r"(c0), "r"(c1), "h"(mask) : "memory");
}
__device__ __forceinline__ void tma_store_2d(const CUtensorMap* map, uint32_t src, int c0, int c1) {
    asm volatile("cp.async.bulk.tensor.2d.global.shared::cta.bulk_group [%0, {%2, %3}], [%1];"
                 ::"l"((uint64_t)map), "r"(src), "r"(c0), "r"(c1) : "memory");
}
__device__ __forceinline__ void tma_commit() { asm volatile("cp.async.bulk.commit_group;" ::: "memory"); }
template <int N> __device__ __forceinline__ void tma_wait_read() { asm volatile("cp.async.bulk.wait_group.read %0;" ::"n"(N) : "memory"); }
template <int N> __device__ __forceinline__ void tma_wait_all() { asm volatile("cp.async.bulk.wait_group %0;" ::"n"(N) : "memory"); }
__device__ __forceinline__ void prefetch_tmap(const CUtensorMap* map) {
    asm volatile("prefetch.tensormap [%0];" ::"l"((uint64_t)map) : "memory");
}
__device__ __forceinline__ void pdl_wait() { asm volatile("griddepcontrol.wait;" ::: "memory"); }
__device__ __forceinline__ void pdl_launch() { asm volatile("griddepcontrol.launch_dependents;" ::: "memory"); }

__device__ __forceinline__ void wgmma_fence() { asm volatile("wgmma.fence.sync.aligned;" ::: "memory"); }
__device__ __forceinline__ void wgmma_commit() { asm volatile("wgmma.commit_group.sync.aligned;" ::: "memory"); }
template <int N> __device__ __forceinline__ void wgmma_wait() { asm volatile("wgmma.wait_group.sync.aligned %0;" ::"n"(N) : "memory"); }
template <int R> __device__ __forceinline__ void reg_alloc() { asm volatile("setmaxnreg.inc.sync.aligned.u32 %0;" ::"n"(R)); }
template <int R> __device__ __forceinline__ void reg_dealloc() { asm volatile("setmaxnreg.dec.sync.aligned.u32 %0;" ::"n"(R)); }
__device__ __forceinline__ void bar_sync(int id, int n) { asm volatile("bar.sync %0, %1;" ::"r"(id), "r"(n) : "memory"); }
__device__ __forceinline__ void bar_arrive(int id, int n) { asm volatile("bar.arrive %0, %1;" ::"r"(id), "r"(n) : "memory"); }

template <int N> __device__ __forceinline__ void fence_regs(float (&d)[N]) {
#pragma unroll
    for (int i = 0; i < N; i++) asm volatile("" : "+f"(d[i])::"memory");
}

__device__ __forceinline__ uint64_t make_desc(uint32_t addr, uint32_t lbo, uint32_t sbo) {
    return (uint64_t)((addr & 0x3FFFF) >> 4) | ((uint64_t)(lbo >> 4) << 16) | ((uint64_t)(sbo >> 4) << 32) | (1ull << 62);
}
__device__ __forceinline__ uint64_t make_desc_nosw(uint32_t addr, uint32_t lbo, uint32_t sbo) {
    return (uint64_t)((addr & 0x3FFFF) >> 4) | ((uint64_t)(lbo >> 4) << 16) | ((uint64_t)(sbo >> 4) << 32);
}
__device__ __forceinline__ uint32_t pack_bf16(float lo, float hi) {
    uint32_t r;
    asm("cvt.rn.bf16x2.f32 %0, %1, %2;" : "=r"(r) : "f"(hi), "f"(lo));
    return r;
}
__device__ __forceinline__ void stmatrix_x4(uint32_t addr, uint32_t r0, uint32_t r1, uint32_t r2, uint32_t r3) {
    asm volatile("stmatrix.sync.aligned.m8n8.x4.shared.b16 [%0], {%1, %2, %3, %4};" ::"r"(addr), "r"(r0), "r"(r1), "r"(r2), "r"(r3) : "memory");
}
__device__ __forceinline__ float ex2(float x) { float y; asm("ex2.approx.ftz.f32 %0, %1;" : "=f"(y) : "f"(x)); return y; }
__device__ __forceinline__ uint32_t bf2_mul(uint32_t a, uint32_t b) { uint32_t r; asm("mul.rn.bf16x2 %0, %1, %2;" : "=r"(r) : "r"(a), "r"(b)); return r; }
__device__ __forceinline__ uint32_t bf2_fma(uint32_t a, uint32_t b, uint32_t c) { uint32_t r; asm("fma.rn.bf16x2 %0, %1, %2, %3;" : "=r"(r) : "r"(a), "r"(b), "r"(c)); return r; }
__device__ __forceinline__ uint32_t bf2_max(uint32_t a, uint32_t b) { uint32_t r; asm("max.bf16x2 %0, %1, %2;" : "=r"(r) : "r"(a), "r"(b)); return r; }
__device__ __forceinline__ float bf_lo(uint32_t v) { return __uint_as_float(v << 16); }
__device__ __forceinline__ float bf_hi(uint32_t v) { return __uint_as_float(v & 0xffff0000u); }

__device__ __forceinline__ void store_acc_to_smem(const float (&d)[64], uint32_t base, int warp_in_wg, int lane, float s0, float s1) {
    const int mi = lane >> 3;
    const int row = warp_in_wg * 16 + (mi & 1) * 8 + (lane & 7);
    const uint32_t rbase = base + row * 128;
#pragma unroll
    for (int b = 0; b < 8; b++) {
        const int chunk = 2 * b + (mi >> 1);
        const uint32_t addr = rbase + (chunk >> 3) * 8192 + (((chunk & 7) ^ (row & 7)) << 4);
        stmatrix_x4(addr, pack_bf16(d[8 * b + 0] * s0, d[8 * b + 1] * s0), pack_bf16(d[8 * b + 2] * s1, d[8 * b + 3] * s1),
                    pack_bf16(d[8 * b + 4] * s0, d[8 * b + 5] * s0), pack_bf16(d[8 * b + 6] * s1, d[8 * b + 7] * s1));
    }
}

template <int H>
__device__ __forceinline__ void store_acc_half(const float (&d)[64], uint32_t base, int warp_in_wg, int lane) {
    const int mi = lane >> 3;
    const int row = warp_in_wg * 16 + (mi & 1) * 8 + (lane & 7);
    const uint32_t rbase = base + row * 128;
#pragma unroll
    for (int bb = 0; bb < 4; bb++) {
        const int b = 4 * H + bb;
        const int chunk = 2 * bb + (mi >> 1);
        stmatrix_x4(rbase + ((chunk ^ (row & 7)) << 4), pack_bf16(d[8 * b + 0], d[8 * b + 1]), pack_bf16(d[8 * b + 2], d[8 * b + 3]),
                    pack_bf16(d[8 * b + 4], d[8 * b + 5]), pack_bf16(d[8 * b + 6], d[8 * b + 7]));
    }
}

template <int TB>
__device__ __forceinline__ void wgmma_m64n128k16_ss(float (&d)[64], uint64_t da, uint64_t db, int scale_d) {
    asm volatile("{\n.reg .pred p;\nsetp.ne.b32 p, %66, 0;\n"
        "wgmma.mma_async.sync.aligned.m64n128k16.f32.bf16.bf16 {%0, %1, %2, %3, %4, %5, %6, %7, %8, %9, %10, %11, %12, %13, %14, %15, %16, %17, %18, %19, %20, %21, %22, %23, %24, %25, %26, %27, %28, %29, %30, %31, %32, %33, %34, %35, %36, %37, %38, %39, %40, %41, %42, %43, %44, %45, %46, %47, %48, %49, %50, %51, %52, %53, %54, %55, %56, %57, %58, %59, %60, %61, %62, %63}, %64, %65, p, 1, 1, 0, %67;\n}\n"
        : "+f"(d[0]), "+f"(d[1]), "+f"(d[2]), "+f"(d[3]), "+f"(d[4]), "+f"(d[5]), "+f"(d[6]), "+f"(d[7]), "+f"(d[8]), "+f"(d[9]), "+f"(d[10]), "+f"(d[11]), "+f"(d[12]), "+f"(d[13]), "+f"(d[14]), "+f"(d[15]), "+f"(d[16]), "+f"(d[17]), "+f"(d[18]), "+f"(d[19]), "+f"(d[20]), "+f"(d[21]), "+f"(d[22]), "+f"(d[23]), "+f"(d[24]), "+f"(d[25]), "+f"(d[26]), "+f"(d[27]), "+f"(d[28]), "+f"(d[29]), "+f"(d[30]), "+f"(d[31]), "+f"(d[32]), "+f"(d[33]), "+f"(d[34]), "+f"(d[35]), "+f"(d[36]), "+f"(d[37]), "+f"(d[38]), "+f"(d[39]), "+f"(d[40]), "+f"(d[41]), "+f"(d[42]), "+f"(d[43]), "+f"(d[44]), "+f"(d[45]), "+f"(d[46]), "+f"(d[47]), "+f"(d[48]), "+f"(d[49]), "+f"(d[50]), "+f"(d[51]), "+f"(d[52]), "+f"(d[53]), "+f"(d[54]), "+f"(d[55]), "+f"(d[56]), "+f"(d[57]), "+f"(d[58]), "+f"(d[59]), "+f"(d[60]), "+f"(d[61]), "+f"(d[62]), "+f"(d[63])
        : "l"(da), "l"(db), "r"(scale_d), "n"(TB));
}
template <int TB>
__device__ __forceinline__ void wgmma_m64n128k16_rs(float (&d)[64], uint32_t a0, uint32_t a1, uint32_t a2, uint32_t a3, uint64_t db, int scale_d) {
    asm volatile("{\n.reg .pred p;\nsetp.ne.b32 p, %69, 0;\n"
        "wgmma.mma_async.sync.aligned.m64n128k16.f32.bf16.bf16 {%0, %1, %2, %3, %4, %5, %6, %7, %8, %9, %10, %11, %12, %13, %14, %15, %16, %17, %18, %19, %20, %21, %22, %23, %24, %25, %26, %27, %28, %29, %30, %31, %32, %33, %34, %35, %36, %37, %38, %39, %40, %41, %42, %43, %44, %45, %46, %47, %48, %49, %50, %51, %52, %53, %54, %55, %56, %57, %58, %59, %60, %61, %62, %63}, {%64, %65, %66, %67}, %68, p, 1, 1, %70;\n}\n"
        : "+f"(d[0]), "+f"(d[1]), "+f"(d[2]), "+f"(d[3]), "+f"(d[4]), "+f"(d[5]), "+f"(d[6]), "+f"(d[7]), "+f"(d[8]), "+f"(d[9]), "+f"(d[10]), "+f"(d[11]), "+f"(d[12]), "+f"(d[13]), "+f"(d[14]), "+f"(d[15]), "+f"(d[16]), "+f"(d[17]), "+f"(d[18]), "+f"(d[19]), "+f"(d[20]), "+f"(d[21]), "+f"(d[22]), "+f"(d[23]), "+f"(d[24]), "+f"(d[25]), "+f"(d[26]), "+f"(d[27]), "+f"(d[28]), "+f"(d[29]), "+f"(d[30]), "+f"(d[31]), "+f"(d[32]), "+f"(d[33]), "+f"(d[34]), "+f"(d[35]), "+f"(d[36]), "+f"(d[37]), "+f"(d[38]), "+f"(d[39]), "+f"(d[40]), "+f"(d[41]), "+f"(d[42]), "+f"(d[43]), "+f"(d[44]), "+f"(d[45]), "+f"(d[46]), "+f"(d[47]), "+f"(d[48]), "+f"(d[49]), "+f"(d[50]), "+f"(d[51]), "+f"(d[52]), "+f"(d[53]), "+f"(d[54]), "+f"(d[55]), "+f"(d[56]), "+f"(d[57]), "+f"(d[58]), "+f"(d[59]), "+f"(d[60]), "+f"(d[61]), "+f"(d[62]), "+f"(d[63])
        : "r"(a0), "r"(a1), "r"(a2), "r"(a3), "l"(db), "r"(scale_d), "n"(TB));
}
template <int SD> __device__ __forceinline__ void wgmma_conv(float (&d)[32], uint32_t a0, uint32_t a1, uint32_t a2, uint32_t a3, uint64_t db) {
    asm volatile("wgmma.mma_async.sync.aligned.m64n64k16.f32.bf16.bf16 {%0, %1, %2, %3, %4, %5, %6, %7, %8, %9, %10, %11, %12, %13, %14, %15, %16, %17, %18, %19, %20, %21, %22, %23, %24, %25, %26, %27, %28, %29, %30, %31}, {%32, %33, %34, %35}, %36, %37, 1, 1, 0;\n"
        : "+f"(d[0]), "+f"(d[1]), "+f"(d[2]), "+f"(d[3]), "+f"(d[4]), "+f"(d[5]), "+f"(d[6]), "+f"(d[7]), "+f"(d[8]), "+f"(d[9]), "+f"(d[10]), "+f"(d[11]), "+f"(d[12]), "+f"(d[13]), "+f"(d[14]), "+f"(d[15]), "+f"(d[16]), "+f"(d[17]), "+f"(d[18]), "+f"(d[19]), "+f"(d[20]), "+f"(d[21]), "+f"(d[22]), "+f"(d[23]), "+f"(d[24]), "+f"(d[25]), "+f"(d[26]), "+f"(d[27]), "+f"(d[28]), "+f"(d[29]), "+f"(d[30]), "+f"(d[31])
        : "r"(a0), "r"(a1), "r"(a2), "r"(a3), "l"(db), "n"(SD));
}
__device__ unsigned int g_attn_next;

constexpr int KV_STAGES = 4;
constexpr int KV_SMEM_W = 0;
constexpr int KV_SMEM_A = 131072;
constexpr int KV_SMEM_STG = KV_SMEM_A + KV_STAGES * 16384;
constexpr int KV_SMEM_BAR = KV_SMEM_STG + 16384;
constexpr int KV_SMEM_TOTAL = KV_SMEM_BAR + 256;

__global__ void __cluster_dims__(2, 1, 1) __launch_bounds__(512, 1)
kv_proj_kernel(const __grid_constant__ CUtensorMap tm_ckv,
               const __grid_constant__ CUtensorMap tm_wuk,
               const __grid_constant__ CUtensorMap tm_wuv,
               const __grid_constant__ CUtensorMap tm_kv_st)
{
    extern __shared__ __align__(1024) uint8_t smem_kv[];
    const uint32_t sb = smem_u32(smem_kv);
    if (sb & 1023u) return;
    TRACE_BEGIN(0);
    const uint32_t bar_w = sb + KV_SMEM_BAR;
    const uint32_t bar_full = bar_w + 64;
    const uint32_t bar_empty = bar_full + 32;
    const int tid = threadIdx.x, wg = tid >> 7, warp = tid >> 5, lane = tid & 31;
    const uint32_t rank = cluster_ctarank();
    const int cid = blockIdx.x >> 1;
    const int mhalf = cid & 1;
    const int nb = (cid >> 1) * 2 + (int)rank;

    if (tid == 0) {
        for (int i = 0; i < 8; i++) mbar_init(bar_w + 8 * i, 1);
        for (int i = 0; i < KV_STAGES; i++) { mbar_init(bar_full + 8 * i, 1); mbar_init(bar_empty + 8 * i, 8); }
        fence_barrier_init();
    }
    __syncthreads();
    cluster_arrive();
    cluster_wait();
    if (blockIdx.x == 0 && threadIdx.x == 0) g_attn_next = 0;
    pdl_launch();

    if (wg == 0) {
        reg_dealloc<40>();
        if (tid == 0) {
            const CUtensorMap* tw = nb < 32 ? &tm_wuk : &tm_wuv;
            const int ncol = (nb & 31) * 128;
            int it = 0;
            for (int t = 0; t < 8; t++) {
                const int mrow = (mhalf * 8 + t) * 128 + rank * 64;
                for (int kc = 0; kc < 8; kc++, it++) {
                    if (t == 0) {
                        mbar_expect_tx(bar_w + 8 * kc, 16384);
                        tma_load_2d(sb + KV_SMEM_W + kc * 16384, tw, bar_w + 8 * kc, ncol, kc * 64);
                        tma_load_2d(sb + KV_SMEM_W + kc * 16384 + 8192, tw, bar_w + 8 * kc, ncol + 64, kc * 64);
                    }
                    const int s = it & (KV_STAGES - 1);
                    mbar_wait(bar_empty + 8 * s, ((it / KV_STAGES) & 1) ^ 1);
                    mbar_expect_tx(bar_full + 8 * s, 16384);
                    tma_load_2d_mc(sb + KV_SMEM_A + s * 16384 + rank * 8192, &tm_ckv, bar_full + 8 * s, kc * 64, mrow, (uint16_t)3);
                }
            }
        }
        __syncwarp();
        cluster_arrive();
        cluster_wait();
    } else {
        reg_alloc<168>();
        const int w = wg - 1, wwarp = warp & 3;
        float acc0[64], acc1[64];
        const uint32_t stg = sb + KV_SMEM_STG;
        const bool el = (tid & 127) == 0;
        for (int t = w; t < 8; t += 2) {
            if (t > 0) bar_sync(3 + w, 256);
#pragma unroll 1
            for (int kc = 0; kc < 8; kc++) {
                const int it = t * 8 + kc;
                const int s = it & (KV_STAGES - 1);
                if (t < 2) mbar_wait(bar_w + 8 * kc, 0);
                mbar_wait(bar_full + 8 * s, (it / KV_STAGES) & 1);
                const uint64_t da = make_desc(sb + KV_SMEM_A + s * 16384, 16, 1024);
                const uint64_t db = make_desc(sb + KV_SMEM_W + kc * 16384, 8192, 1024);
                wgmma_fence();
#pragma unroll
                for (int k = 0; k < 4; k++) {
                    wgmma_m64n128k16_ss<1>(acc0, da + (k * 32 >> 4), db + (k * 2048 >> 4), (kc | k) != 0);
                    wgmma_m64n128k16_ss<1>(acc1, da + ((8192 + k * 32) >> 4), db + (k * 2048 >> 4), (kc | k) != 0);
                }
                wgmma_commit();
                if (kc > 0) {
                    wgmma_wait<1>();
                    const int ps = (it - 1) & (KV_STAGES - 1);
                    if (lane < 2) mbar_arrive_cluster(bar_empty + 8 * ps, lane);
                }
            }
            if (t < 7) bar_arrive(4 - w, 256);
            wgmma_wait<0>();
            fence_regs(acc0); fence_regs(acc1);
            {
                const int ps = (t * 8 + 7) & (KV_STAGES - 1);
                if (lane < 2) mbar_arrive_cluster(bar_empty + 8 * ps, lane);
            }
            const int grow = nb * SEQ + (mhalf * 8 + t) * 128;
            if (t > 0) bar_sync(5 + ((t - 1) & 1), 160);
#define KV_CHUNK(ACC, H, C, ROW) \
            if (C >= 2) { if (el) tma_wait_read<1>(); bar_sync(1 + w, 128); } \
            store_acc_half<H>(ACC, stg + (C & 1) * 8192, wwarp, lane); \
            fence_proxy_async(); \
            bar_sync(1 + w, 128); \
            if (el) { tma_store_2d(&tm_kv_st, stg + (C & 1) * 8192, H * 64, ROW); tma_commit(); }
            KV_CHUNK(acc0, 0, 0, grow)
            KV_CHUNK(acc0, 1, 1, grow)
            KV_CHUNK(acc1, 0, 2, grow + 64)
            KV_CHUNK(acc1, 1, 3, grow + 64)
#undef KV_CHUNK
            if (t < 7 && wwarp == 0) {
                if (el) tma_wait_read<0>();
                __syncwarp();
                bar_arrive(5 + (t & 1), 160);
            }
        }
        if ((tid & 127) == 0) tma_wait_all<0>();
        TRACE_END(0, (tid & 127) == 0);
        __syncwarp();
        cluster_arrive();
        cluster_wait();
    }
}

constexpr int AT_STAGES = 6;
constexpr int AT_SMEM_STG = AT_STAGES * 32768;
constexpr int AT_SMEM_BAR = AT_SMEM_STG + 32768;
constexpr int AT_SMEM_TOTAL = AT_SMEM_BAR + 256 + 1024;
constexpr int AT_MAX_ITEMS = 8;
constexpr int AT_GRID = 132;
struct AttnSched { uint16_t item[AT_GRID][AT_MAX_ITEMS]; };

constexpr uint32_t SC_HI = 0x3DB53DB5u;
constexpr uint32_t SC_LO = 0x371E371Eu;
constexpr float LOG2E = 1.4426950408889634f;

template <bool MASK, bool FIRST>
__device__ __forceinline__ void softmax_step(float (&s)[64], float& m0, float& m1, float& l0, float& l1,
                                             float& sc0, float& sc1, int row0, int t4) {
    uint32_t mx0 = 0xFF80FF80u, mx1 = 0xFF80FF80u;
    uint32_t p[32];
#pragma unroll
    for (int i = 0; i < 32; i++) {
        uint32_t v = pack_bf16(s[2 * i], s[2 * i + 1]);
        v = bf2_fma(v, SC_HI, bf2_mul(v, SC_LO));
        if (MASK) {
            const int col = (i >> 1) * 8 + 2 * t4;
            const int row = row0 + (i & 1) * 8;
            if (col > row) v = 0xFF80FF80u;
            else if (col + 1 > row) v = (v & 0xFFFFu) | 0xFF800000u;
        }
        p[i] = v;
        if (i & 1) mx1 = bf2_max(mx1, v); else mx0 = bf2_max(mx0, v);
    }
    uint32_t a = __byte_perm(mx0, mx1, 0x5410);
    uint32_t b = __byte_perm(mx0, mx1, 0x7632);
    uint32_t mx = bf2_max(a, b);
    mx = bf2_max(mx, __shfl_xor_sync(0xffffffffu, mx, 1));
    mx = bf2_max(mx, __shfl_xor_sync(0xffffffffu, mx, 2));
    float n0 = bf_lo(mx), n1 = bf_hi(mx);
    if (!FIRST) {
        n0 = fmaxf(n0, m0); n1 = fmaxf(n1, m1);
        sc0 = ex2((m0 - n0) * LOG2E); sc1 = ex2((m1 - n1) * LOG2E);
    }
    m0 = n0; m1 = n1;
    const float b0 = -n0 * LOG2E, b1 = -n1 * LOG2E;
    float a0 = 0.f, a1 = 0.f, c0 = 0.f, c1 = 0.f;
#pragma unroll
    for (int i = 0; i < 32; i++) {
        const float bb = (i & 1) ? b1 : b0;
        const float e0 = ex2(fmaf(bf_lo(p[i]), LOG2E, bb));
        const float e1 = ex2(fmaf(bf_hi(p[i]), LOG2E, bb));
        if (i & 1) { a1 += e0; c1 += e1; } else { a0 += e0; c0 += e1; }
        s[2 * i] = e0; s[2 * i + 1] = e1;
    }
    if (FIRST) { l0 = a0 + c0; l1 = a1 + c1; }
    else { l0 = l0 * sc0 + (a0 + c0); l1 = l1 * sc1 + (a1 + c1); }
}

__global__ void __launch_bounds__(384, 1)
attn_kernel(const __grid_constant__ CUtensorMap tm_x,
            const __grid_constant__ CUtensorMap tm_wq,
            const __grid_constant__ CUtensorMap tm_kv,
            const __grid_constant__ CUtensorMap tm_ctx,
            const __grid_constant__ AttnSched sched)
{
    extern __shared__ uint8_t smem_raw[];
    const uint32_t sb = (smem_u32(smem_raw) + 1023) & ~1023u;
    TRACE_BEGIN(1);
    const uint32_t bar_full = sb + AT_SMEM_BAR;
    const uint32_t bar_empty = bar_full + 64;
    const int tid = threadIdx.x, wg = tid >> 7, warp = tid >> 5, lane = tid & 31;

    if (tid == 0) {
        for (int i = 0; i < AT_STAGES; i++) { mbar_init(bar_full + 8 * i, 1); mbar_init(bar_empty + 8 * i, 8); }
        fence_barrier_init();
    }
    __syncthreads();
    pdl_launch();

    if (wg == 0) {
        reg_dealloc<24>();
        if (tid == 0) {
            int s = 0; uint32_t ph = 1;
            bool waited = false;
            int item = blockIdx.x;
            for (;;) {
                if (item >= NH * 16) {
                    mbar_wait(bar_empty + 8 * s, ph);
                    asm volatile("st.shared.u32 [%0], %1;" ::"r"(bar_full + 128 + 4 * s), "r"(item) : "memory");
                    mbar_arrive(bar_full + 8 * s);
                    break;
                }
                const int h = item & 31, qb = 15 - (item >> 5);
                for (int kc = 0; kc < 8; kc++) {
                    mbar_wait(bar_empty + 8 * s, ph);
                    const uint32_t st = sb + s * 32768, fb = bar_full + 8 * s;
                    if (kc == 0) asm volatile("st.shared.u32 [%0], %1;" ::"r"(bar_full + 128 + 4 * s), "r"(item) : "memory");
                    mbar_expect_tx(fb, 32768);
                    tma_load_2d(st, &tm_x, fb, kc * 64, qb * 128);
                    tma_load_2d(st + 16384, &tm_wq, fb, h * 128, kc * 64);
                    tma_load_2d(st + 24576, &tm_wq, fb, h * 128 + 64, kc * 64);
                    if (++s == AT_STAGES) { s = 0; ph ^= 1; }
                }
                if (!waited) { pdl_wait(); waited = true; }
                const int krow = h * SEQ, vrow = (NH + h) * SEQ;
                for (int j = qb; j >= -1; j--) {
                    if (j == 0) item = (int)atomicAdd(&g_attn_next, 1u) + AT_GRID;
                    if (j >= 0) {
                        mbar_wait(bar_empty + 8 * s, ph);
                        const uint32_t st = sb + s * 32768, fb = bar_full + 8 * s;
                        mbar_expect_tx(fb, 32768);
                        tma_load_2d(st, &tm_kv, fb, 0, krow + j * 128);
                        tma_load_2d(st + 16384, &tm_kv, fb, 64, krow + j * 128);
                        if (++s == AT_STAGES) { s = 0; ph ^= 1; }
                    }
                    if (j < qb) {
                        mbar_wait(bar_empty + 8 * s, ph);
                        const uint32_t st = sb + s * 32768, fb = bar_full + 8 * s;
                        mbar_expect_tx(fb, 32768);
                        tma_load_2d(st, &tm_kv, fb, 0, vrow + (j + 1) * 128);
                        tma_load_2d(st + 16384, &tm_kv, fb, 64, vrow + (j + 1) * 128);
                        if (++s == AT_STAGES) { s = 0; ph ^= 1; }
                    }
                }
            }
        }
    } else {
        reg_alloc<240>();
        const int w = wg - 1, wwarp = warp & 3;
        const int t4 = lane & 3;
        const int row0 = w * 64 + wwarp * 16 + (lane >> 2);
        const uint32_t stg = sb + AT_SMEM_STG + w * 16384;
        float o[64], sacc[64];
        uint32_t qf[32], pf[32];
        int s = 0; uint32_t ph = 0;
        if (w == 1) bar_arrive(1, 256);
#define AT_ADV() do { if (++s == AT_STAGES) { s = 0; ph ^= 1; } } while (0)
#define AT_RELEASE(st) do { if (lane == 0) mbar_arrive(bar_empty + 8 * (st)); } while (0)
        for (int n = 0; n < NH * 16; n++) {
            int item;
            mbar_wait(bar_full + 8 * s, ph);
            asm volatile("ld.shared.u32 %0, [%1];" : "=r"(item) : "r"(bar_full + 128 + 4 * s) : "memory");
            item = __shfl_sync(0xffffffffu, item, 0);
            if (item >= NH * 16) break;
            const int h = item & 31, qb = 15 - (item >> 5);
            int ps = 0;
#pragma unroll 1
            for (int kc = 0; kc < 8; kc++) {
                mbar_wait(bar_full + 8 * s, ph);
                const uint32_t st = sb + s * 32768;
                const uint64_t da = make_desc(st + w * 8192, 16, 1024);
                const uint64_t db = make_desc(st + 16384, 8192, 1024);
                wgmma_fence();
#pragma unroll
                for (int k = 0; k < 4; k++)
                    wgmma_m64n128k16_ss<1>(sacc, da + (k * 32 >> 4), db + (k * 2048 >> 4), (kc | k) != 0);
                wgmma_commit();
                if (kc > 0) { wgmma_wait<1>(); AT_RELEASE(ps); }
                ps = s;
                AT_ADV();
            }
            wgmma_wait<0>();
            fence_regs(sacc);
            AT_RELEASE(ps);
#pragma unroll
            for (int i = 0; i < 32; i++) qf[i] = pack_bf16(sacc[2 * i], sacc[2 * i + 1]);

            float m0, m1, l0, l1, sc0, sc1;
            {
                bar_sync(1 + w, 256);
                mbar_wait(bar_full + 8 * s, ph);
                const uint64_t dk = make_desc(sb + s * 32768, 16, 1024);
                wgmma_fence();
#pragma unroll
                for (int k = 0; k < 8; k++)
                    wgmma_m64n128k16_rs<0>(sacc, qf[4 * k], qf[4 * k + 1], qf[4 * k + 2], qf[4 * k + 3],
                                           dk + (((k >> 2) * 16384 + (k & 3) * 32) >> 4), k != 0);
                wgmma_commit();
                bar_arrive(2 - w, 256);
                wgmma_wait<0>();
                fence_regs(sacc);
                AT_RELEASE(s);
                AT_ADV();
                softmax_step<true, true>(sacc, m0, m1, l0, l1, sc0, sc1, row0, t4);
#pragma unroll
                for (int i = 0; i < 32; i++) pf[i] = pack_bf16(sacc[2 * i], sacc[2 * i + 1]);
            }
#pragma unroll 1
            for (int j = qb - 1; j >= 0; j--) {
                bar_sync(1 + w, 256);
                const int sk = s;
                mbar_wait(bar_full + 8 * s, ph);
                const uint64_t dk = make_desc(sb + s * 32768, 16, 1024);
                wgmma_fence();
#pragma unroll
                for (int k = 0; k < 8; k++)
                    wgmma_m64n128k16_rs<0>(sacc, qf[4 * k], qf[4 * k + 1], qf[4 * k + 2], qf[4 * k + 3],
                                           dk + (((k >> 2) * 16384 + (k & 3) * 32) >> 4), k != 0);
                wgmma_commit();
                AT_ADV();
                const int sv = s;
                mbar_wait(bar_full + 8 * s, ph);
                const uint64_t dv = make_desc(sb + s * 32768, 16384, 1024);
                const int first = (j == qb - 1);
                wgmma_fence();
#pragma unroll
                for (int k = 0; k < 8; k++)
                    wgmma_m64n128k16_rs<1>(o, pf[4 * k], pf[4 * k + 1], pf[4 * k + 2], pf[4 * k + 3],
                                           dv + ((k * 2048) >> 4), (k != 0) || !first);
                wgmma_commit();
                AT_ADV();
                bar_arrive(2 - w, 256);
                wgmma_wait<1>();
                fence_regs(sacc);
                AT_RELEASE(sk);
                softmax_step<false, false>(sacc, m0, m1, l0, l1, sc0, sc1, row0, t4);
                fence_regs(sacc);
                wgmma_wait<0>();
                fence_regs(o);
                fence_regs(sacc);
                AT_RELEASE(sv);
#pragma unroll
                for (int i = 0; i < 16; i++) {
                    o[4 * i] *= sc0; o[4 * i + 1] *= sc0; o[4 * i + 2] *= sc1; o[4 * i + 3] *= sc1;
                }
#pragma unroll
                for (int i = 0; i < 32; i++) pf[i] = pack_bf16(sacc[2 * i], sacc[2 * i + 1]);
            }
            {
                bar_sync(1 + w, 256);
                mbar_wait(bar_full + 8 * s, ph);
                const uint64_t dv = make_desc(sb + s * 32768, 16384, 1024);
                wgmma_fence();
#pragma unroll
                for (int k = 0; k < 8; k++)
                    wgmma_m64n128k16_rs<1>(o, pf[4 * k], pf[4 * k + 1], pf[4 * k + 2], pf[4 * k + 3],
                                           dv + ((k * 2048) >> 4), (k != 0) || (qb != 0));
                wgmma_commit();
                bar_arrive(2 - w, 256);
                l0 += __shfl_xor_sync(0xffffffffu, l0, 1); l0 += __shfl_xor_sync(0xffffffffu, l0, 2);
                l1 += __shfl_xor_sync(0xffffffffu, l1, 1); l1 += __shfl_xor_sync(0xffffffffu, l1, 2);
                const float i0 = 1.f / l0, i1 = 1.f / l1;
                if ((tid & 127) == 0) tma_wait_read<0>();
                bar_sync(3 + w, 128);
                wgmma_wait<0>();
                fence_regs(o);
                AT_RELEASE(s);
                AT_ADV();
                store_acc_to_smem(o, stg, wwarp, lane, i0, i1);
                fence_proxy_async();
                bar_sync(3 + w, 128);
                if ((tid & 127) == 0) {
                    tma_store_2d(&tm_ctx, stg, h * 128, qb * 128 + w * 64);
                    tma_store_2d(&tm_ctx, stg + 8192, h * 128 + 64, qb * 128 + w * 64);
                    tma_commit();
                }
            }
        }
        if ((tid & 127) == 0) tma_wait_all<0>();
        TRACE_END(1, (tid & 127) == 0);
#undef AT_ADV
#undef AT_RELEASE
    }
}

constexpr int OP_STAGES = 6;
constexpr int OP_SMEM_BAR = OP_STAGES * 32768;
constexpr int OP_SMEM_TOTAL = OP_SMEM_BAR + 256 + 1024;

__global__ void __cluster_dims__(2, 1, 1) __launch_bounds__(384, 1)
out_proj_kernel(const __grid_constant__ CUtensorMap tm_ctx,
                const __grid_constant__ CUtensorMap tm_wo,
                const __grid_constant__ CUtensorMap tm_out)
{
    extern __shared__ uint8_t smem_raw[];
    const uint32_t sb = (smem_u32(smem_raw) + 1023) & ~1023u;
    TRACE_BEGIN(2);
    const uint32_t bar_full = sb + OP_SMEM_BAR;
    const uint32_t bar_empty = bar_full + 64;
    const int tid = threadIdx.x, wg = tid >> 7, warp = tid >> 5, lane = tid & 31;
    const uint32_t rank = cluster_ctarank();
    const int tile = blockIdx.x >> 1;
    const int mt = tile >> 2, nt = tile & 3;
    if (tid == 0) {
        for (int i = 0; i < OP_STAGES; i++) { mbar_init(bar_full + 8 * i, 1); mbar_init(bar_empty + 8 * i, 8); }
        fence_barrier_init();
    }
    __syncthreads();
    constexpr int KITERS = 32;
    if (wg == 0) {
        reg_dealloc<40>();
        if (tid == 0) {
            int s = 0; uint32_t ph = 1;
            for (int kc = 0; kc < OP_STAGES; kc++) {
                const uint32_t st = sb + kc * 32768, fb = bar_full + 8 * kc;
                const int k0 = (rank * KITERS + kc) * 64;
                mbar_expect_tx(fb, 32768);
                tma_load_2d(st + 16384, &tm_wo, fb, nt * 128, k0);
                tma_load_2d(st + 24576, &tm_wo, fb, nt * 128 + 64, k0);
            }
            pdl_wait();
            TRACE_END(6, true);
            for (int kc = 0; kc < KITERS; kc++) {
                const uint32_t st = sb + s * 32768, fb = bar_full + 8 * s;
                const int k0 = (rank * KITERS + kc) * 64;
                if (kc >= OP_STAGES) {
                    mbar_wait(bar_empty + 8 * s, ph);
                    mbar_expect_tx(fb, 32768);
                    tma_load_2d(st + 16384, &tm_wo, fb, nt * 128, k0);
                    tma_load_2d(st + 24576, &tm_wo, fb, nt * 128 + 64, k0);
                }
                tma_load_2d(st, &tm_ctx, fb, k0, mt * 128);
                if (++s == OP_STAGES) { s = 0; ph ^= 1; }
            }
        }
        __syncwarp();
        cluster_arrive(); cluster_wait();
        cluster_arrive(); cluster_wait();
    } else {
        reg_alloc<232>();
        const int w = wg - 1, wwarp = warp & 3;
        float acc[64];
        int s = 0, ps = 0; uint32_t ph = 0;
#pragma unroll 1
        for (int kc = 0; kc < KITERS; kc++) {
            mbar_wait(bar_full + 8 * s, ph);
            const uint32_t st = sb + s * 32768;
            const uint64_t da = make_desc(st + w * 8192, 16, 1024);
            const uint64_t db = make_desc(st + 16384, 8192, 1024);
            wgmma_fence();
#pragma unroll
            for (int k = 0; k < 4; k++)
                wgmma_m64n128k16_ss<1>(acc, da + (k * 32 >> 4), db + (k * 2048 >> 4), (kc | k) != 0);
            wgmma_commit();
            if (kc > 0) { wgmma_wait<1>(); if (lane == 0) mbar_arrive(bar_empty + 8 * ps); }
            ps = s;
            if (++s == OP_STAGES) { s = 0; ph ^= 1; }
        }
        wgmma_wait<0>();
        fence_regs(acc);
        cluster_arrive(); cluster_wait();
        const int t = tid & 127;
        if (w != (int)rank) {
            uint32_t ra;
            asm volatile("mapa.shared::cluster.u32 %0, %1, %2;" : "=r"(ra) : "r"(sb), "r"(rank ^ 1));
#pragma unroll
            for (int i = 0; i < 16; i++)
                asm volatile("st.shared::cluster.v4.f32 [%0], {%1, %2, %3, %4};" ::"r"(ra + (i * 128 + t) * 16),
                             "f"(acc[4 * i]), "f"(acc[4 * i + 1]), "f"(acc[4 * i + 2]), "f"(acc[4 * i + 3]) : "memory");
        }
        cluster_arrive(); cluster_wait();
        if (w == (int)rank) {
#pragma unroll
            for (int i = 0; i < 16; i++) {
                float4 v;
                asm volatile("ld.shared.v4.f32 {%0, %1, %2, %3}, [%4];" : "=f"(v.x), "=f"(v.y), "=f"(v.z), "=f"(v.w) : "r"(sb + (i * 128 + t) * 16));
                acc[4 * i] += v.x; acc[4 * i + 1] += v.y; acc[4 * i + 2] += v.z; acc[4 * i + 3] += v.w;
            }
            const uint32_t stg = sb + 65536;
            store_acc_to_smem(acc, stg, wwarp, lane, 1.f, 1.f);
            fence_proxy_async();
            bar_sync(1, 128);
            if (t == 0) {
                tma_store_2d(&tm_out, stg, nt * 128, mt * 128 + w * 64);
                tma_store_2d(&tm_out, stg + 8192, nt * 128 + 64, mt * 128 + w * 64);
                tma_commit();
                tma_wait_all<0>();
                TRACE_END(2, true);
            }
        }
    }
}

constexpr int SS_U_BYTES = 2 * 192 * 16;
constexpr int SS_KQ = 648;
constexpr int SS_KP_WORDS = 2176;
constexpr int SS_SMEM_U = 0;
constexpr int SS_SMEM_KQ = SS_U_BYTES;
constexpr int SS_SMEM_KP = SS_SMEM_KQ + SS_KQ * 4;
constexpr int SS_SMEM_BAR = SS_SMEM_KP + SS_KP_WORDS * 4;
constexpr int SS_SMEM_TOTAL = SS_SMEM_BAR + 16;

__device__ __align__(1024) bf16 g_y[(size_t)SSM_D * SEQ];

__device__ __align__(1024) bf16 g_ut[(size_t)SSM_D * (SS_U_BYTES / 2)];
__global__ void __launch_bounds__(512, 4) ssm_tin_kernel(const bf16* __restrict__ u) {
    __shared__ __align__(16) uint32_t tile[128][33];
    pdl_launch();
    TRACE_BEGIN(3);
    const int tid = threadIdx.x, c0 = (blockIdx.x & 15) * 32, ag = blockIdx.x >> 4;
#pragma unroll
    for (int it = 0; it < 1; it++) {
        const int idx = tid, rp = idx >> 2, cc = (idx & 3) * 8;
        const bf16* p = u + (size_t)(ag * 256 + rp * 2) * SSM_D + c0 + cc;
        const uint4 r0 = *reinterpret_cast<const uint4*>(p), r1 = *reinterpret_cast<const uint4*>(p + SSM_D);
        uint32_t* t = &tile[rp][cc];
        t[0] = __byte_perm(r0.x, r1.x, 0x5410); t[1] = __byte_perm(r0.x, r1.x, 0x7632);
        t[2] = __byte_perm(r0.y, r1.y, 0x5410); t[3] = __byte_perm(r0.y, r1.y, 0x7632);
        t[4] = __byte_perm(r0.z, r1.z, 0x5410); t[5] = __byte_perm(r0.z, r1.z, 0x7632);
        t[6] = __byte_perm(r0.w, r1.w, 0x5410); t[7] = __byte_perm(r0.w, r1.w, 0x7632);
    }
    __syncthreads();
    uint4* dst = reinterpret_cast<uint4*>(g_ut);
#pragma unroll
    for (int it = 0; it < 2; it++) {
        const int idx = tid + it * 512, al = 15 - (idx & 15), kc = (idx >> 4) & 1, c = idx >> 5;
        const int rp = al * 8 + kc * 4;
        dst[(size_t)(c0 + c) * 384 + kc * 192 + 127 - (ag * 16 + al)] = make_uint4(tile[rp][c], tile[rp + 1][c], tile[rp + 2][c], tile[rp + 3][c]);
    }
#pragma unroll
    for (int it = 0; it < 1; it++) {
        const int idx = tid, sl = idx & 15, c = idx >> 4;
        dst[(size_t)(c0 + c) * 384 + (ag >> 2) * 192 + 128 + (ag & 3) * 16 + sl] = make_uint4(0, 0, 0, 0);
    }
    TRACE_END(3, threadIdx.x == 0);
}

__global__ void __launch_bounds__(128) ssm_tout_kernel(const bf16* __restrict__ u, const bf16* __restrict__ D_skip, bf16* __restrict__ out) {
    __shared__ __align__(16) bf16 tile[32][136];
    const int tid = threadIdx.x, c0 = (blockIdx.x & 15) * 32, l0 = (blockIdx.x >> 4) * 128;
    TRACE_BEGIN(5);
    uint4 uv[4];
#pragma unroll
    for (int it = 0; it < 4; it++) {
        const int idx = tid + it * 128, r = idx >> 2, cc = (idx & 3) * 8;
        uv[it] = *reinterpret_cast<const uint4*>(u + (size_t)(l0 + r) * SSM_D + c0 + cc);
    }
    const uint4 dv = *reinterpret_cast<const uint4*>(D_skip + c0 + (tid & 3) * 8);
    pdl_wait();
#pragma unroll
    for (int it = 0; it < 4; it++) {
        const int idx = tid + it * 128, c = idx >> 4, ll = (idx & 15) * 8;
        *reinterpret_cast<uint4*>(&tile[c][ll]) = *reinterpret_cast<const uint4*>(g_y + (size_t)(c0 + c) * SEQ + l0 + ll);
    }
    __syncthreads();
#pragma unroll
    for (int it = 0; it < 4; it++) {
        const int idx = tid + it * 128, r = idx >> 2, cc = (idx & 3) * 8;
        const uint32_t uu[4] = {uv[it].x, uv[it].y, uv[it].z, uv[it].w}, dd[4] = {dv.x, dv.y, dv.z, dv.w};
        uint32_t o[4];
#pragma unroll
        for (int k = 0; k < 4; k++) {
            const uint32_t ud = pack_bf16(bf_lo(uu[k]) * bf_lo(dd[k]), bf_hi(uu[k]) * bf_hi(dd[k]));
            o[k] = pack_bf16(__bfloat162float(tile[cc + 2 * k][r]) + bf_lo(ud), __bfloat162float(tile[cc + 2 * k + 1][r]) + bf_hi(ud));
        }
        *reinterpret_cast<uint4*>(out + (size_t)(l0 + r) * 1024 + 512 + c0 + cc) = make_uint4(o[0], o[1], o[2], o[3]);
    }
    TRACE_END(5, threadIdx.x == 0);
}

__device__ __forceinline__ void mma_tf32(float (&d)[4], float a0, float a1, float a2, float a3, float b0, float b1) {
    asm volatile("mma.sync.aligned.m16n8k8.row.col.f32.tf32.tf32.f32 {%0,%1,%2,%3}, {%4,%5,%6,%7}, {%8,%9}, {%0,%1,%2,%3};"
                 : "+f"(d[0]), "+f"(d[1]), "+f"(d[2]), "+f"(d[3])
                 : "r"(__float_as_uint(a0)), "r"(__float_as_uint(a1)), "r"(__float_as_uint(a2)), "r"(__float_as_uint(a3)),
                   "r"(__float_as_uint(b0)), "r"(__float_as_uint(b1)));
}
__device__ __forceinline__ float rn_tf32(float x) { return __uint_as_float((__float_as_uint(x) + 0x1000u) & 0xffffe000u); }
__device__ __forceinline__ float2 cexp_p(float ar2, float air, float p) {
    const float mag = ex2(ar2 * p);
    float r = air * p;
    r = r - ((r + 12582912.f) - 12582912.f);
    const float ang = r * 6.283185307179586f;
    return make_float2(mag * __cosf(ang), mag * __sinf(ang));
}
__device__ __forceinline__ float2 cmul(float2 a, float2 b) { return make_float2(a.x * b.x - a.y * b.y, a.x * b.y + a.y * b.x); }

__global__ void __launch_bounds__(128, 4)
ssm_main_kernel(const bf16* __restrict__ log_A_real, const bf16* __restrict__ A_imag, const bf16* __restrict__ C_real,
                const bf16* __restrict__ C_imag, const bf16* __restrict__ log_dt)
{
    extern __shared__ __align__(128) uint8_t sp[];
    const uint32_t sb = smem_u32(sp);
    const int t = threadIdx.x, w = t >> 5, lane = t & 31, g = lane >> 2, t4 = lane & 3;
    const int d = blockIdx.x;
    TRACE_BEGIN(4);
    pdl_launch();
    float* KQ = reinterpret_cast<float*>(sp + SS_SMEM_KQ);
    uint32_t* KP = reinterpret_cast<uint32_t*>(sp + SS_SMEM_KP);
    if (t == 0) { mbar_init(sb + SS_SMEM_BAR, 1); fence_barrier_init(); }
    float4* PR = reinterpret_cast<float4*>(sp + SS_SMEM_KP);
    {
        const int idx = d * SSM_N + t;
        const float dt = __bfloat162float(__float2bfloat16_rn(expf(__bfloat162float(log_dt[d]))));
        const float ea = __bfloat162float(__float2bfloat16_rn(expf(__bfloat162float(log_A_real[idx]))));
        const float are = -ea * dt, aim = __bfloat162float(A_imag[idx]) * dt;
        const float cr = 2.f * (__bfloat162float(C_real[idx]) * dt), ci = 2.f * (__bfloat162float(C_imag[idx]) * dt);
        const float ar2 = are * LOG2E, air = aim * 0.15915494309189535f;
        const float2 z64 = cexp_p(ar2, air, 64.f), z128 = cexp_p(ar2, air, 128.f), z2k = cexp_p(ar2, air, 2048.f);
        PR[t * 3 + 0] = make_float4(ar2, air, cr, ci);
        PR[t * 3 + 1] = make_float4(z64.x, z64.y, z128.x, z128.y);
        PR[t * 3 + 2] = make_float4(rn_tf32(z2k.x), rn_tf32(z2k.y), 0.f, 0.f);
    }
    __syncwarp();
    float acc3[3][2][4];
#pragma unroll
    for (int i = 0; i < 3; i++)
#pragma unroll
        for (int j = 0; j < 2; j++)
#pragma unroll
            for (int k = 0; k < 4; k++) acc3[i][j][k] = 0.f;
    {
        const float p0 = (float)g, p2 = (float)(256 + 128 * (g >> 2) + 2 * (g & 3)), p3 = (float)(512 + 128 * (g >> 1) + 4 * (g & 1)),
                    p4 = (float)(1024 + 128 * g), pc = (float)(8 * g);
#pragma unroll 2
        for (int ks = 0; ks < 8; ks++) {
            const int n = w * 32 + ks * 4 + t4;
            const float4 pa = PR[n * 3], pb = PR[n * 3 + 1];
            const float2 x5 = *reinterpret_cast<const float2*>(&PR[n * 3 + 2]);
            float2 x[5];
            x[0] = cexp_p(pa.x, pa.y, p0);
            x[1] = cmul(x[0], make_float2(pb.z, pb.w));
            x[2] = cexp_p(pa.x, pa.y, p2);
            x[3] = cexp_p(pa.x, pa.y, p3);
            x[4] = cexp_p(pa.x, pa.y, p4);
            const float2 w0 = cmul(cexp_p(pa.x, pa.y, pc), make_float2(pa.z, pa.w));
            const float2 w1 = cmul(w0, make_float2(pb.x, pb.y));
#pragma unroll
            for (int r = 0; r < 5; r++) { x[r].x = rn_tf32(x[r].x); x[r].y = rn_tf32(x[r].y); }
            const float b00 = rn_tf32(w0.x), b01 = rn_tf32(-w0.y), b10 = rn_tf32(w1.x), b11 = rn_tf32(-w1.y);
            mma_tf32(acc3[0][0], x[0].x, x[1].x, x[0].y, x[1].y, b00, b01);
            mma_tf32(acc3[0][1], x[0].x, x[1].x, x[0].y, x[1].y, b10, b11);
            mma_tf32(acc3[1][0], x[2].x, x[3].x, x[2].y, x[3].y, b00, b01);
            mma_tf32(acc3[1][1], x[2].x, x[3].x, x[2].y, x[3].y, b10, b11);
            mma_tf32(acc3[2][0], x[4].x, x5.x, x[4].y, x5.y, b00, b01);
            mma_tf32(acc3[2][1], x[4].x, x5.x, x[4].y, x5.y, b10, b11);
        }
    }
    __syncthreads();
    if (t == 0) {
        pdl_wait();
        mbar_expect_tx(sb + SS_SMEM_BAR, SS_U_BYTES);
        asm volatile("cp.async.bulk.shared::cluster.global.mbarrier::complete_tx::bytes [%0], [%1], %2, [%3];"
                     ::"r"(sb + SS_SMEM_U), "l"(g_ut + (size_t)d * (SS_U_BYTES / 2)), "n"(SS_U_BYTES), "r"(sb + SS_SMEM_BAR) : "memory");
    }
    {
        float* P = KQ + w * SS_KQ;
#pragma unroll
        for (int j = 0; j < 2; j++)
#pragma unroll
            for (int e = 0; e < 2; e++) {
                const int col = 8 * j + 2 * t4 + e;
                P[g + 8 * col] = acc3[0][j][e];
                P[128 + g + 8 * col] = acc3[0][j][2 + e];
                P[256 + 64 * (g >> 2) + (g & 3) + 4 * col] = acc3[1][j][e];
                P[384 + 32 * (g >> 1) + (g & 1) + 2 * col] = acc3[1][j][2 + e];
                P[512 + 16 * g + col] = acc3[2][j][e];
            }
        if (lane == 0) P[640] = acc3[2][0][2];
    }
    __syncthreads();
    {
        float v[6];
#pragma unroll
        for (int i = 0; i < 6; i++) {
            const int q = t + 128 * i;
            v[i] = (q < 641) ? (KQ[q] + KQ[SS_KQ + q]) + (KQ[2 * SS_KQ + q] + KQ[3 * SS_KQ + q]) : 0.f;
        }
#pragma unroll
        for (int i = 0; i < 6; i++) { const int q = t + 128 * i; if (q < SS_KQ) KQ[q] = v[i]; }
    }
    __syncthreads();
    {
        auto kval = [&](int l) -> float {
            const int qb = (int)(__bfloat16_as_ushort(__float2bfloat16_rn((float)l))) - 17024;
            const int q = (l < 0 || l >= SEQ) ? 641 : (l < 128 ? l : qb);
            return KQ[q];
        };
        float prev = kval(17 * t - 65);
#pragma unroll
        for (int i = 0; i < 17; i++) {
            const float k = kval(17 * t - 64 + i);
            KP[17 * t + i] = pack_bf16(k, prev);
            prev = k;
        }
    }
    __syncthreads();
    float accA[32], accB[32];
    {
        const uint32_t* kp = KP + 64 + (g - 2 * t4) + 16 * w;
        const uint64_t db0 = make_desc_nosw(sb + SS_SMEM_U, 3072, 128);
        mbar_wait(sb + SS_SMEM_BAR, 0);
#pragma unroll
        for (int bt = 0; bt < 8; bt++) {
            uint32_t x[16];
#pragma unroll
            for (int q = 0; q < 4; q++) {
                const uint32_t* k = kp + 64 * (4 * bt + q);
                x[4 * q + 0] = k[0]; x[4 * q + 1] = k[8]; x[4 * q + 2] = k[-8];
                asm volatile("mov.b32 %0, %1;" : "=r"(x[4 * q + 3]) : "r"(x[4 * q]));
            }
            wgmma_fence();
#pragma unroll
            for (int q = 0; q < 4; q++) {
                if (bt == 0 && q == 0) {
                    wgmma_conv<0>(accA, x[0], x[1], x[2], x[3], db0);
                    wgmma_conv<0>(accB, x[0], x[1], x[2], x[3], db0 + 64);
                } else {
                    wgmma_conv<1>(accA, x[4 * q], x[4 * q + 1], x[4 * q + 2], x[4 * q + 3], db0 + (uint64_t)(4 * (4 * bt + q)));
                    if (bt < 4) wgmma_conv<1>(accB, x[4 * q], x[4 * q + 1], x[4 * q + 2], x[4 * q + 3], db0 + (uint64_t)(64 + 4 * (4 * bt + q)));
                }
            }
            wgmma_commit();
            wgmma_wait<0>();
#pragma unroll
            for (int q = 0; q < 16; q++) asm volatile("" : "+r"(x[q])::"memory");
        }
        fence_regs(accA); fence_regs(accB);
    }
    __syncthreads();
    {
        float* Yb = reinterpret_cast<float*>(sp) + (w & 1) * 2176;
        float2* Y = reinterpret_cast<float2*>(Yb + g * 136 + 126 + w + (w & 1) - 2 * t4);
#define SS_OFF(i) ((((i) >> 1) & 1) * 544 - 4 * ((i) >> 2))
#define SS_ACC(i) ((i) < 32 ? accA[(i) & 31] : accB[(i) & 31])
        if (w >= 2) {
#pragma unroll
            for (int i = 0; i < 64; i += 2) Y[SS_OFF(i)] = make_float2(SS_ACC(i + 1), SS_ACC(i));
        } else if (lane < 16 + 16 * w) {
            *reinterpret_cast<float2*>(Yb + (lane & 15) * 136 + (lane >> 4) * 2) = make_float2(0.f, 0.f);
        }
        __syncthreads();
        if (w < 2) {
#pragma unroll
            for (int i = 0; i < 64; i += 2) {
                const float2 v = Y[SS_OFF(i)];
                Y[SS_OFF(i)] = make_float2(SS_ACC(i + 1) + v.x, SS_ACC(i) + v.y);
            }
        }
        __syncthreads();
        const float* Y0 = reinterpret_cast<const float*>(sp);
#pragma unroll
        for (int it = 0; it < 2; it++) {
            const int c = t + it * 128, a = c >> 1, b0 = (c & 1) * 8;
            float v[8];
#pragma unroll
            for (int e = 0; e < 8; e++) { const int o = (b0 + e) * 136 + a; v[e] = Y0[o] + Y0[2177 + o]; }
            *reinterpret_cast<uint4*>(g_y + (size_t)d * SEQ + c * 8) =
                make_uint4(pack_bf16(v[0], v[1]), pack_bf16(v[2], v[3]), pack_bf16(v[4], v[5]), pack_bf16(v[6], v[7]));
        }
        TRACE_END(4, threadIdx.x == 0);
    }
}

typedef CUresult (*EncodeFn)(CUtensorMap*, CUtensorMapDataType, cuuint32_t, void*, const cuuint64_t*, const cuuint64_t*,
                             const cuuint32_t*, const cuuint32_t*, CUtensorMapInterleave, CUtensorMapSwizzle,
                             CUtensorMapL2promotion, CUtensorMapFloatOOBfill);

static CUtensorMap make_map(EncodeFn enc, const void* ptr, uint64_t cols, uint64_t rows, uint32_t bc, uint32_t br) {
    CUtensorMap m;
    cuuint64_t dims[2] = {cols, rows};
    cuuint64_t strides[1] = {cols * 2};
    cuuint32_t box[2] = {bc, br};
    cuuint32_t es[2] = {1, 1};
    enc(&m, CU_TENSOR_MAP_DATA_TYPE_BFLOAT16, 2, const_cast<void*>(ptr), dims, strides, box, es, CU_TENSOR_MAP_INTERLEAVE_NONE,
        CU_TENSOR_MAP_SWIZZLE_128B, CU_TENSOR_MAP_L2_PROMOTION_L2_256B, CU_TENSOR_MAP_FLOAT_OOB_FILL_NONE);
    return m;
}

template <typename... KArgs, typename... Args>
static void launch(void (*kern)(KArgs...), int grid, int block, int smem, cudaStream_t st, bool pdl, Args... args) {
    cudaLaunchConfig_t cfg = {};
    cfg.gridDim = dim3(grid); cfg.blockDim = dim3(block); cfg.dynamicSmemBytes = smem; cfg.stream = st;
    cudaLaunchAttribute at[1];
    at[0].id = cudaLaunchAttributeProgrammaticStreamSerialization;
    at[0].val.programmaticStreamSerializationAllowed = 1;
    cfg.attrs = at; cfg.numAttrs = pdl ? 1 : 0;
    cudaLaunchKernelEx(&cfg, kern, args...);
}

constexpr int TOUT_PAD = 45056;
extern "C" void kernel_launch(void* const* d_in, const int* in_sizes, int n_in, void* d_out, int out_size) {
    static bool init = false;
    static CUtensorMap tm_ckv, tm_wuk, tm_wuv, tm_kv_st, tm_x, tm_wq, tm_kv, tm_ctx_st, tm_ctx, tm_wo, tm_out;
    static AttnSched sched;
    static cudaStream_t st2;
    static cudaEvent_t ev_fork, ev_join;
    static void* last_in[6] = {0, 0, 0, 0, 0, 0};
    static void* last_out = 0;
    bool same = init && last_out == d_out;
    for (int i = 0; i < 6; i++) same = same && last_in[i] == d_in[i];
    if (!same) {
        void* fn = nullptr;
        cudaDriverEntryPointQueryResult qr;
        cudaGetDriverEntryPoint("cuTensorMapEncodeTiled", &fn, cudaEnableDefault, &qr);
        EncodeFn enc = (EncodeFn)fn;
        void *kv, *ctx;
        cudaGetSymbolAddress(&kv, g_kv);
        cudaGetSymbolAddress(&ctx, g_ctx);
        tm_x = make_map(enc, d_in[0], DM, SEQ, 64, 128);
        tm_ckv = make_map(enc, d_in[1], DC, SEQ, 64, 64);
        tm_wq = make_map(enc, d_in[2], NH * HD, DM, 64, 64);
        tm_wuk = make_map(enc, d_in[3], NH * HD, DC, 64, 64);
        tm_wuv = make_map(enc, d_in[4], NH * HD, DC, 64, 64);
        tm_wo = make_map(enc, d_in[5], DM, NH * HD, 64, 64);
        tm_kv_st = make_map(enc, kv, HD, 2 * NH * SEQ, 64, 64);
        tm_kv = make_map(enc, kv, HD, 2 * NH * SEQ, 64, 128);
        tm_ctx_st = make_map(enc, ctx, NH * HD, SEQ, 64, 64);
        tm_ctx = make_map(enc, ctx, NH * HD, SEQ, 64, 128);
        tm_out = make_map(enc, d_out, 1024, SEQ, 64, 64);
        cudaFuncSetAttribute(kv_proj_kernel, cudaFuncAttributeMaxDynamicSharedMemorySize, KV_SMEM_TOTAL);
        cudaFuncSetAttribute(attn_kernel, cudaFuncAttributeMaxDynamicSharedMemorySize, AT_SMEM_TOTAL);
        cudaFuncSetAttribute(out_proj_kernel, cudaFuncAttributeMaxDynamicSharedMemorySize, OP_SMEM_TOTAL);
        cudaFuncSetAttribute(ssm_main_kernel, cudaFuncAttributePreferredSharedMemoryCarveout, 100);
        cudaFuncSetAttribute(ssm_tout_kernel, cudaFuncAttributeMaxDynamicSharedMemorySize, TOUT_PAD);
        cudaFuncSetAttribute(ssm_tin_kernel, cudaFuncAttributePreferredSharedMemoryCarveout, 100);
        cudaFuncSetAttribute(ssm_tout_kernel, cudaFuncAttributePreferredSharedMemoryCarveout, 100);
        if (!init) {
            cudaStreamCreateWithFlags(&st2, cudaStreamNonBlocking);
            cudaEventCreateWithFlags(&ev_fork, cudaEventDisableTiming);
            cudaEventCreateWithFlags(&ev_join, cudaEventDisableTiming);
        }
        float load[AT_GRID]; int cnt[AT_GRID];
        for (int c = 0; c < AT_GRID; c++) { const float x = (float)c / (AT_GRID - 1); load[c] = 0.f * x; cnt[c] = 0; for (int n = 0; n < AT_MAX_ITEMS; n++) sched.item[c][n] = 0xFFFF; }
        for (int qb = 15; qb >= 0; qb--)
            for (int h = 0; h < NH; h++) {
                int best = 0;
                for (int c = 1; c < AT_GRID; c++) if (load[c] < load[best]) best = c;
                sched.item[best][cnt[best]++] = (uint16_t)(h * 16 + qb);
                load[best] += (float)qb + 3.7f;
            }
        for (int i = 0; i < 6; i++) last_in[i] = d_in[i];
        last_out = d_out;
        init = true;
    }
    cudaStream_t st = cudaStreamPerThread;
    cudaEventRecord(ev_fork, st);
    cudaStreamWaitEvent(st2, ev_fork, 0);
    launch(kv_proj_kernel, 128, 384, KV_SMEM_TOTAL, st, false, tm_ckv, tm_wuk, tm_wuv, tm_kv_st);
    launch(ssm_tin_kernel, 128, 512, 0, st2, false, (const bf16*)d_in[6]);
    launch(ssm_main_kernel, SSM_D, 128, SS_SMEM_TOTAL, st2, true, (const bf16*)d_in[7], (const bf16*)d_in[8], (const bf16*)d_in[9],
           (const bf16*)d_in[10], (const bf16*)d_in[11]);
    launch(ssm_tout_kernel, 256, 128, TOUT_PAD, st2, true, (const bf16*)d_in[6], (const bf16*)d_in[12], (bf16*)d_out);
    cudaEventRecord(ev_join, st2);
    launch(attn_kernel, AT_GRID, 384, AT_SMEM_TOTAL, st, true, tm_x, tm_wq, tm_kv, tm_ctx_st, sched);
    launch(out_proj_kernel, 128, 384, OP_SMEM_TOTAL, st, true, tm_ctx, tm_wo, tm_out);
    cudaStreamWaitEvent(st, ev_join, 0);
}
```
